```python
import torch

def _softmax(x, axis=-1):
    return torch.softmax(x, dim=axis)
def _gelu(x):
    return torch.nn.functional.gelu(x, approximate="tanh")
def _silu(x):
    return torch.nn.functional.silu(x)
def _sigmoid(x):
    return torch.sigmoid(x)
def _layernorm(x, axis=-1, eps=1e-5):
    m = x.mean(dim=axis, keepdim=True)
    v = x.var(dim=axis, keepdim=True, unbiased=False)
    return (x - m) / torch.sqrt(v + eps)
def _scatter_add(tgt, idx, src, axis=0):
    return tgt.clone().index_add_(axis, idx, src)
def _segment_sum(src, seg, n):
    out = torch.zeros((n,) + src.shape[1:], dtype=src.dtype)
    return out.index_add_(0, seg, src)
def _pad(x, pw):
    flat = tuple(v for pair in reversed(pw) for v in pair)
    return torch.nn.functional.pad(x, flat)

kernel_name = 'standalone__kv_cache_quant_int4_int2_kv_with_per_channel_or_per_token_scales__decode'

def setup_inputs():

    _w = (lambda a: (lambda t: t.to(torch.bfloat16) if t.is_floating_point() else t)(torch.as_tensor(a)))
    B = 1
    Sq = 1
    Skv = 65536
    Hq = 32
    Hkv = 16
    Dh = 128
    bits = 4
    G = -1
    if G <= 0 or G >= Skv:
        G = max(1, Skv // 2)
    Skv = (Skv // G) * G
    ngk = Skv // G
    qmax = (1 << bits) - 1
    return {
        "q": _w((lambda *s: torch.randn(*s, dtype=torch.bfloat16) * 1.6)(B, Hq, Sq, Dh)),
        "qk": _w(torch.randint(0, qmax + 1, (B, Hkv, Skv, Dh)).to(torch.int32)),
        "qv": _w(torch.randint(0, qmax + 1, (B, Hkv, Skv, Dh)).to(torch.int32)),
        "k_scales": _w(torch.abs((lambda *s: torch.randn(*s, dtype=torch.bfloat16) * 1.6)(B, Hkv, ngk, Dh)) * 0.05 + 0.02),
        "k_zeros": _w((lambda *s: torch.randn(*s, dtype=torch.bfloat16) * 1.6)(B, Hkv, ngk, Dh) + float(qmax) / 2.0),
        "v_scales": _w(torch.abs((lambda *s: torch.randn(*s, dtype=torch.bfloat16) * 0.05)(B, Hkv, Skv, 1)) * 0.05 + 0.02),
        "v_zeros": _w((lambda *s: torch.randn(*s, dtype=torch.bfloat16) * 0.05)(B, Hkv, Skv, 1) + float(qmax) / 2.0),
    }

def reference(q, qk, qv, k_scales, k_zeros, v_scales, v_zeros):
    B, Hq, Sq, Dh = q.shape
    Hkv, Skv = qk.shape[1], qk.shape[2]
    ngk = k_scales.shape[2]
    G = Skv // ngk
    ks = (lambda x, n, axis: torch.repeat_interleave(x, n, dim=axis))(k_scales, G, axis=2)
    kz = (lambda x, n, axis: torch.repeat_interleave(x, n, dim=axis))(k_zeros, G, axis=2)
    k = ((lambda x, dt: x.to(dt))(qk, q.dtype) - kz) * ks
    v = ((lambda x, dt: x.to(dt))(qv, q.dtype) - v_zeros) * v_scales
    rep = Hq // Hkv
    if rep > 1:
        k = (lambda x, n, axis: torch.repeat_interleave(x, n, dim=axis))(k, rep, axis=1)
        v = (lambda x, n, axis: torch.repeat_interleave(x, n, dim=axis))(v, rep, axis=1)
    scale = float(Dh) ** -0.5
    logits = torch.einsum("bhqd,bhkd->bhqk", q, k) * scale
    p = _softmax(logits, axis=-1)
    o = torch.einsum("bhqk,bhkd->bhqd", p, v)
    return o
```

```cpp
#include <cuda_runtime.h>
#include <cuda_bf16.h>
#include <stdint.h>

namespace kvq {

constexpr int HQ = 32;
constexpr int HKV = 16;
constexpr int SKV = 65536;
constexpr int DH = 128;
constexpr int NGK = 2;
constexpr int TILE = 32;
constexpr int UNIT = 16;
constexpr int UNITS_PER_SEG = SKV / NGK / UNIT;
constexpr int NUNITS = HKV * SKV / UNIT;
#define KVQ_NK 2
#define KVQ_NV 2
#define KVQ_NHALF 0
#define KVQ_NSLOT 2
#define KVQ_PRE 0
#define KVQ_DELAY 4
constexpr int NK = KVQ_NK;
constexpr int NV = KVQ_NV;
static_assert(NV <= NK && NK < 8, "ring sizes");
constexpr int NHALF = KVQ_NHALF;
constexpr int NFULL = (NUNITS - NHALF) / 2;
constexpr int NTICKETS = NFULL + NHALF;
constexpr int NSLOT = KVQ_NSLOT;
constexpr int KV_TILE_BYTES = TILE * DH * 4;
constexpr int SC_BYTES = TILE * 2;
constexpr int KSLOT_BYTES = KV_TILE_BYTES + 2 * SC_BYTES;
constexpr int NCW = 8;
constexpr int NTHREADS = (NCW + 2) * 32;
constexpr int MAXG = 160;
constexpr int NSLICE = 128;
constexpr int NSEG = HKV * NGK;

constexpr int OFF_K = 0;
constexpr int OFF_V = OFF_K + NK * KSLOT_BYTES;
constexpr int OFF_TAB = OFF_V + NV * KV_TILE_BYTES;
constexpr int OFF_BIAS = OFF_TAB + NSEG * 2 * DH * 4;
constexpr int OFF_RED = OFF_BIAS + NSEG * 2 * 4;
constexpr int OFF_ML = OFF_RED + NCW * 2 * DH * 4;
constexpr int OFF_BAR = OFF_ML + NCW * 2 * 8;
constexpr int OFF_TID = OFF_BAR + (2 * NK + 2 * NV + 1) * 8;
constexpr int OFF_FLAG = OFF_TID + 32;
constexpr int SMEM_BYTES = OFF_FLAG + 16;

constexpr float NEG_BIG = -3.0e38f;

__device__ uint4 g_part[NSLOT * MAXG * NSLICE];
__device__ unsigned long long g_ticket;
#define TRACE(i)

__device__ __forceinline__ uint32_t smem_u32(const void* p) { return (uint32_t)__cvta_generic_to_shared(p); }
__device__ __forceinline__ void mbar_init(uint32_t bar, uint32_t cnt) {
    asm volatile("mbarrier.init.shared::cta.b64 [%0], %1;" ::"r"(bar), "r"(cnt) : "memory");
}
__device__ __forceinline__ void mbar_expect_tx(uint32_t bar, uint32_t bytes) {
    asm volatile("mbarrier.arrive.expect_tx.shared::cta.b64 _, [%0], %1;" ::"r"(bar), "r"(bytes) : "memory");
}
__device__ __forceinline__ void mbar_arrive(uint32_t bar) {
    asm volatile("mbarrier.arrive.shared::cta.b64 _, [%0];" ::"r"(bar) : "memory");
}
__device__ __forceinline__ void mbar_wait(uint32_t bar, uint32_t parity) {
    uint32_t done;
    uint32_t it = 0;
    do {
        asm volatile(
            "{\n.reg .pred p;\n"
            "mbarrier.try_wait.parity.shared::cta.b64 p, [%1], %2;\n"
            "selp.u32 %0, 1, 0, p;\n}"
            : "=r"(done)
            : "r"(bar), "r"(parity)
            : "memory");
        if (++it > (1u << 26)) __trap();
    } while (!done);
}
__device__ __forceinline__ uint4 ldg128(const void* p) {
    uint4 v;
    asm volatile("ld.global.nc.v4.u32 {%0,%1,%2,%3}, [%4];" : "=r"(v.x), "=r"(v.y), "=r"(v.z), "=r"(v.w) : "l"(p));
    return v;
}
__device__ __forceinline__ float bf_lo(uint32_t x) { return __uint_as_float(x << 16); }
__device__ __forceinline__ float bf_hi(uint32_t x) { return __uint_as_float(x & 0xffff0000u); }
__device__ __forceinline__ void bulk_g2s_hint(uint32_t dst, const void* src, uint32_t bytes, uint32_t bar, uint64_t pol) {
    asm volatile(
        "cp.async.bulk.shared::cluster.global.mbarrier::complete_tx::bytes.L2::cache_hint [%0], [%1], %2, [%3], %4;" ::"r"(dst),
        "l"(src), "r"(bytes), "r"(bar), "l"(pol)
        : "memory");
}
__device__ __forceinline__ float ex2(float x) {
    float y;
    asm("ex2.approx.ftz.f32 %0, %1;" : "=f"(y) : "f"(x));
    return y;
}
__device__ __forceinline__ int4 lds128(uint32_t addr) {
    int4 v;
    asm volatile("ld.shared.v4.s32 {%0,%1,%2,%3}, [%4];" : "=r"(v.x), "=r"(v.y), "=r"(v.z), "=r"(v.w) : "r"(addr));
    return v;
}
__device__ __forceinline__ uint2 lds64(uint32_t addr) {
    uint2 v;
    asm volatile("ld.shared.v2.u32 {%0,%1}, [%2];" : "=r"(v.x), "=r"(v.y) : "r"(addr));
    return v;
}
__device__ __forceinline__ float lds_bf16(uint32_t addr) {
    unsigned short v;
    asm volatile("ld.shared.u16 %0, [%1];" : "=h"(v) : "r"(addr));
    return __uint_as_float(((uint32_t)v) << 16);
}
__device__ __forceinline__ void st_chunk(uint4* p, uint32_t a, uint32_t b, uint32_t c, uint32_t d) {
    asm volatile("st.relaxed.gpu.global.v4.u32 [%0], {%1,%2,%3,%4};" ::"l"(p), "r"(a), "r"(b), "r"(c), "r"(d) : "memory");
}
__device__ __forceinline__ void ld_chunks5(uint4 (&v)[5], const uint4* p, uint32_t pend) {
    asm volatile(
        "{\n.reg .pred p0, p1, p2, p3, p4;\n.reg .b32 t;\n"
        "and.b32 t, %21, 1;  setp.ne.u32 p0, t, 0;\n"
        "and.b32 t, %21, 2;  setp.ne.u32 p1, t, 0;\n"
        "and.b32 t, %21, 4;  setp.ne.u32 p2, t, 0;\n"
        "and.b32 t, %21, 8;  setp.ne.u32 p3, t, 0;\n"
        "and.b32 t, %21, 16; setp.ne.u32 p4, t, 0;\n"
        "@p0 ld.relaxed.gpu.global.v4.u32 {%0,%1,%2,%3}, [%20];\n"
        "@p1 ld.relaxed.gpu.global.v4.u32 {%4,%5,%6,%7}, [%20+65536];\n"
        "@p2 ld.relaxed.gpu.global.v4.u32 {%8,%9,%10,%11}, [%20+131072];\n"
        "@p3 ld.relaxed.gpu.global.v4.u32 {%12,%13,%14,%15}, [%20+196608];\n"
        "@p4 ld.relaxed.gpu.global.v4.u32 {%16,%17,%18,%19}, [%20+262144];\n"
        "}"
        : "+r"(v[0].x), "+r"(v[0].y), "+r"(v[0].z), "+r"(v[0].w), "+r"(v[1].x), "+r"(v[1].y), "+r"(v[1].z), "+r"(v[1].w),
          "+r"(v[2].x), "+r"(v[2].y), "+r"(v[2].z), "+r"(v[2].w), "+r"(v[3].x), "+r"(v[3].y), "+r"(v[3].z), "+r"(v[3].w),
          "+r"(v[4].x), "+r"(v[4].y), "+r"(v[4].z), "+r"(v[4].w)
        : "l"(p), "r"(pend)
        : "memory");
}
static_assert(MAXG == 160 && NSLICE * 32 * 16 == 65536, "ld_chunks5 layout");
__device__ __forceinline__ void consumer_bar() { asm volatile("bar.sync 1, %0;" ::"n"(NCW * 32) : "memory"); }
__device__ __forceinline__ float warp_max(float x) {
    int i = __float_as_int(x);
    i ^= (i >> 31) & 0x7fffffff;
    i = __reduce_max_sync(0xffffffffu, i);
    i ^= (i >> 31) & 0x7fffffff;
    return __int_as_float(i);
}

__global__ void __launch_bounds__(NTHREADS, 1)
kvq_decode_kernel(const __nv_bfloat16* __restrict__ q, const int* __restrict__ qk, const int* __restrict__ qv,
                  const __nv_bfloat16* __restrict__ k_scales, const __nv_bfloat16* __restrict__ k_zeros,
                  const __nv_bfloat16* __restrict__ v_scales, const __nv_bfloat16* __restrict__ v_zeros,
                  __nv_bfloat16* __restrict__ out)
{
    extern __shared__ __align__(128) unsigned char smem[];
    const uint32_t sb = smem_u32(smem);
    const int tid = threadIdx.x, warp = tid >> 5, lane = tid & 31;
    const int G = gridDim.x, cta = blockIdx.x;
    const uint32_t bar_fk = sb + OFF_BAR, bar_ek = bar_fk + NK * 8, bar_fv = bar_ek + NK * 8, bar_ev = bar_fv + NV * 8,
                   bar_post = bar_ev + NV * 8;
    volatile int* tile_ids = reinterpret_cast<volatile int*>(smem + OFF_TID);
    volatile int* combined = reinterpret_cast<volatile int*>(smem + OFF_FLAG);
    volatile uint32_t* tagbase = reinterpret_cast<volatile uint32_t*>(combined + 1);
    unsigned long long draw = 0;

    uint64_t pol;
    asm volatile("createpolicy.fractional.L2::evict_first.b64 %0, 1.0;" : "=l"(pol));
    auto issue_k = [&](int s, int u, bool half) {
        const uint32_t kvb = half ? KV_TILE_BYTES / 2 : KV_TILE_BYTES;
        const uint32_t scb = half ? SC_BYTES / 2 : SC_BYTES;
        const uint32_t fk = bar_fk + s * 8;
        const uint32_t dst = sb + OFF_K + s * KSLOT_BYTES;
        tile_ids[s] = u * 2 + (half ? 1 : 0);
        mbar_expect_tx(fk, kvb + 2 * scb);
        bulk_g2s_hint(dst, qk + (size_t)u * (UNIT * DH), kvb, fk, pol);
        bulk_g2s_hint(dst + KV_TILE_BYTES, v_scales + (size_t)u * UNIT, scb, fk, pol);
        bulk_g2s_hint(dst + KV_TILE_BYTES + SC_BYTES, v_zeros + (size_t)u * UNIT, scb, fk, pol);
    };
    auto issue_v = [&](int s, int u, bool half) {
        const uint32_t kvb = half ? KV_TILE_BYTES / 2 : KV_TILE_BYTES;
        const uint32_t fv = bar_fv + s * 8;
        mbar_expect_tx(fv, kvb);
        bulk_g2s_hint(sb + OFF_V + s * KV_TILE_BYTES, qv + (size_t)u * (UNIT * DH), kvb, fv, pol);
    };

    uint4 pq0, pq1, pks0, pks1, pkz0, pkz1;
    if (warp < NCW) {
        const int off = (tid >> 4) * (2 * DH) + (tid & 15) * 8;
        pq0 = ldg128(q + off);
        pq1 = ldg128(q + off + DH);
        pks0 = ldg128(k_scales + off);
        pks1 = ldg128(k_scales + off + DH);
        pkz0 = ldg128(k_zeros + off);
        pkz1 = ldg128(k_zeros + off + DH);
    } else if (lane == 0) {
        if (warp == NCW) {
            TRACE(0);
            draw = atomicAdd(&g_ticket, 1ull);
            *combined = 0;
            mbar_init(bar_post, 1);
#pragma unroll
            for (int s = 0; s < NK; s++) mbar_init(bar_ek + s * 8, NCW);
#pragma unroll
            for (int s = 0; s < NV; s++) mbar_init(bar_ev + s * 8, NCW);
        } else {
#pragma unroll
            for (int s = 0; s < NK; s++) mbar_init(bar_fk + s * 8, 1);
#pragma unroll
            for (int s = 0; s < NV; s++) mbar_init(bar_fv + s * 8, 1);
            asm volatile("fence.proxy.async.shared::cta;" ::: "memory");
#pragma unroll
            for (int s = 0; s < NK; s++) {
                const int u = 2 * (cta + s * G);
                issue_k(s, u, false);
                if (s < NV) issue_v(s, u, false);
                if (s == 0) TRACE(13);
            }
            TRACE(14);
        }
    }
    __syncthreads();

    if (warp == NCW) {
        if (lane == 0) {
            const unsigned int ndraws = (unsigned int)(NTICKETS - NK * G + G);
            const unsigned long long epoch = draw / ndraws;
            const unsigned long long base = epoch * ndraws - (unsigned long long)(NK * G);
            *tagbase = (uint32_t)epoch * 16u + 1u;
            int sk = 0, sv = 0;
            uint32_t phk = 0, phv = 0;
#pragma unroll
            for (int i = NV; i < NK; i++) {
                mbar_wait(bar_ev + sv * 8, phv);
                issue_v(sv, 2 * (cta + i * G), false);
                if (++sv == NV) { sv = 0; phv ^= 1; }
            }
            while (true) {
                mbar_wait(bar_ek + sk * 8, phk);
                if (draw == ~0ull) draw = atomicAdd(&g_ticket, 1ull);
                const int t = (int)(draw - base);
                if (t >= NTICKETS) {
                    TRACE(2);
                    tile_ids[sk] = -1;
                    mbar_arrive(bar_fk + sk * 8);
                    break;
                }
                const bool half = (NHALF > 0) && (t >= NFULL);
                const int u = half ? (t + NFULL) : (2 * t);
                issue_k(sk, u, half);
                if (++sk == NK) { sk = 0; phk ^= 1; }
                mbar_wait(bar_ev + sv * 8, phv);
                issue_v(sv, u, half);
                if (++sv == NV) { sv = 0; phv ^= 1; }
                draw = ~0ull;
            }
        }
    } else if (warp == NCW + 1) {
        constexpr int KMAX = MAXG / 32;
        uint32_t valid = 0;
#pragma unroll
        for (int k = 0; k < KMAX; k++) valid |= (lane + 32 * k < G) ? (1u << k) : 0u;
        for (int h = 0; h < HKV; h++) {
            __syncwarp();
            uint32_t it;
            mbar_wait(bar_post, (uint32_t)(h & 1));
            if (h != HKV - 1) {
#pragma unroll 1
                for (int i = 0; i < KVQ_DELAY; i++) __nanosleep(1000);
            }
            const uint32_t tag = *tagbase + (uint32_t)h;
            for (int jj = cta; jj < NSLICE || jj == cta; jj += G) {
                const int j = jj % NSLICE;
                const uint4* base = g_part + ((size_t)(h % NSLOT) * MAXG + lane) * NSLICE + j;
                uint4 v[KMAX];
#pragma unroll
                for (int k = 0; k < KMAX; k++) v[k] = make_uint4(0u, 0u, __float_as_uint(NEG_BIG), tag);
                uint32_t pend = valid;
                it = 0;
                while (true) {
                    ld_chunks5(v, base, pend);
#pragma unroll
                    for (int k = 0; k < KMAX; k++)
                        if (v[k].w == tag) pend &= ~(1u << k);
                    if (__all_sync(0xffffffffu, pend == 0u)) break;
                    if (h != HKV - 1) __nanosleep(500);
                    if (++it > (1u << 24)) __trap();
                }
                if (lane == 0) TRACE(6);
                float M = NEG_BIG;
#pragma unroll
                for (int k = 0; k < KMAX; k++) M = fmaxf(M, __uint_as_float(v[k].z));
                M = warp_max(M);
                float a0 = 0.f, a1 = 0.f, L = 0.f;
#pragma unroll
                for (int k = 0; k < KMAX; k++) {
                    const float f = ex2(__uint_as_float(v[k].z) - M);
                    a0 = fmaf(f, __uint_as_float(v[k].x), a0);
                    a1 = fmaf(f, __uint_as_float(v[k].y), a1);
                    L += f;
                }
#pragma unroll
                for (int o = 16; o > 0; o >>= 1) {
                    a0 += __shfl_xor_sync(0xffffffffu, a0, o);
                    a1 += __shfl_xor_sync(0xffffffffu, a1, o);
                    L += __shfl_xor_sync(0xffffffffu, L, o);
                }
                if (lane == 0 && jj < NSLICE) {
                    __nv_bfloat162 o2 = __floats2bfloat162_rn(__fdividef(a0, L), __fdividef(a1, L));
                    *reinterpret_cast<__nv_bfloat162*>(out + (2 * h + (j >> 6)) * DH + 2 * (j & 63)) = o2;
                    TRACE(7);
                }
                __syncwarp();
            }
            if (lane == 0) *combined = h + 1;
        }
    } else {
        const int g = lane >> 3, c = lane & 7, par = lane & 1;
        float a0[16], a1[16], acc0[4], acc1[4];
        float bias = 0.f, m = NEG_BIG, l = 0.f;
#pragma unroll
        for (int i = 0; i < 16; i++) a0[i] = a1[i] = 0.f;
#pragma unroll
        for (int i = 0; i < 4; i++) acc0[i] = acc1[i] = 0.f;
        int cur_seg = -1, cur_head = 0;
        float* red = reinterpret_cast<float*>(smem + OFF_RED);
        float2* ml = reinterpret_cast<float2*>(smem + OFF_ML);
        uint4* mybox = g_part + (size_t)cta * NSLICE + tid;

        auto wait_combined = [&](int h) {
            uint32_t it = 0;
            while (*combined < h) {
                __nanosleep(100);
                if (++it > (1u << 26)) __trap();
            }
        };
        auto flush = [&](bool have, int upto) {
            if (have) {
                float ls = l + __shfl_xor_sync(0xffffffffu, l, 8);
                ls += __shfl_xor_sync(0xffffffffu, ls, 16);
                float* dst = red + warp * 2 * DH + 4 * lane;
                *reinterpret_cast<float4*>(dst) = make_float4(acc0[0], acc0[1], acc0[2], acc0[3]);
                *reinterpret_cast<float4*>(dst + DH) = make_float4(acc1[0], acc1[1], acc1[2], acc1[3]);
                if (lane < 2) ml[warp * 2 + lane] = make_float2(m, ls);
                const uint32_t tag = *tagbase + (uint32_t)cur_head;
                wait_combined(cur_head);
                consumer_bar();
                if (tid < NSLICE) {
                    const int hh = tid >> 6, d = 2 * (tid & 63);
                    float2 w[NCW], xv[NCW];
#pragma unroll
                    for (int i = 0; i < NCW; i++) w[i] = ml[i * 2 + hh];
#pragma unroll
                    for (int i = 0; i < NCW; i++) xv[i] = *reinterpret_cast<const float2*>(red + (i * 2 + hh) * DH + d);
                    float M = fmaxf(fmaxf(fmaxf(w[0].x, w[1].x), fmaxf(w[2].x, w[3].x)),
                                    fmaxf(fmaxf(w[4].x, w[5].x), fmaxf(w[6].x, w[7].x)));
                    float x0 = 0.f, x1 = 0.f, L = 0.f;
#pragma unroll
                    for (int i = 0; i < NCW; i++) {
                        const float f = ex2(w[i].x - M);
                        x0 = fmaf(f, xv[i].x, x0);
                        x1 = fmaf(f, xv[i].y, x1);
                        L = fmaf(f, w[i].y, L);
                    }
                    st_chunk(mybox + (size_t)(cur_head % NSLOT) * MAXG * NSLICE, __float_as_uint(__fdividef(x0, L)),
                             __float_as_uint(__fdividef(x1, L)), __float_as_uint(M + __log2f(L)), tag);
                    if (tid == 0) mbar_arrive(bar_post);
                }
                cur_head++;
            }
            for (; cur_head < upto; cur_head++) {
                if (tid < NSLICE) {
                    wait_combined(cur_head);
                    st_chunk(mybox + (size_t)(cur_head % NSLOT) * MAXG * NSLICE, 0u, 0u, __float_as_uint(NEG_BIG),
                             *tagbase + (uint32_t)cur_head);
                    if (tid == 0) mbar_arrive(bar_post);
                }
            }
            if (have) consumer_bar();
            __syncwarp();
        };

        {
            const float sc = 0.08838834764831845f * 1.4426950408889634f;
            const uint32_t q0w[4] = {pq0.x, pq0.y, pq0.z, pq0.w}, q1w[4] = {pq1.x, pq1.y, pq1.z, pq1.w};
            const uint32_t ksw[2][4] = {{pks0.x, pks0.y, pks0.z, pks0.w}, {pks1.x, pks1.y, pks1.z, pks1.w}};
            const uint32_t kzw[2][4] = {{pkz0.x, pkz0.y, pkz0.z, pkz0.w}, {pkz1.x, pkz1.y, pkz1.z, pkz1.w}};
            float* tab = reinterpret_cast<float*>(smem + OFF_TAB) + (tid >> 4) * (NGK * 2 * DH) + (tid & 15) * 8;
#pragma unroll
            for (int gg = 0; gg < NGK; gg++) {
                float t0[8], t1[8], b0 = 0.f, b1 = 0.f;
#pragma unroll
                for (int i = 0; i < 4; i++) {
                    const float sl = bf_lo(ksw[gg][i]) * sc, sh = bf_hi(ksw[gg][i]) * sc;
                    t0[2 * i] = bf_lo(q0w[i]) * sl;
                    t0[2 * i + 1] = bf_hi(q0w[i]) * sh;
                    t1[2 * i] = bf_lo(q1w[i]) * sl;
                    t1[2 * i + 1] = bf_hi(q1w[i]) * sh;
                    b0 = fmaf(t0[2 * i], bf_lo(kzw[gg][i]), b0);
                    b0 = fmaf(t0[2 * i + 1], bf_hi(kzw[gg][i]), b0);
                    b1 = fmaf(t1[2 * i], bf_lo(kzw[gg][i]), b1);
                    b1 = fmaf(t1[2 * i + 1], bf_hi(kzw[gg][i]), b1);
                }
                float4* d0 = reinterpret_cast<float4*>(tab + gg * 2 * DH);
                float4* d1 = reinterpret_cast<float4*>(tab + gg * 2 * DH + DH);
                d0[0] = make_float4(t0[0], t0[1], t0[2], t0[3]);
                d0[1] = make_float4(t0[4], t0[5], t0[6], t0[7]);
                d1[0] = make_float4(t1[0], t1[1], t1[2], t1[3]);
                d1[1] = make_float4(t1[4], t1[5], t1[6], t1[7]);
#pragma unroll
                for (int o = 1; o < 16; o <<= 1) {
                    b0 += __shfl_xor_sync(0xffffffffu, b0, o);
                    b1 += __shfl_xor_sync(0xffffffffu, b1, o);
                }
                if ((tid & 15) == 0)
                    *reinterpret_cast<float2*>(smem + OFF_BIAS + ((tid >> 4) * NGK + gg) * 8) = make_float2(b0, b1);
            }
            consumer_bar();
        }

        int sk = 0, sv = 0;
        uint32_t phk = 0, phv = 0;
        const uint32_t k_off = (uint32_t)(OFF_K + (warp * 4 + g) * (DH * 4) + c * 16);
        const uint32_t v_off = (uint32_t)(OFF_V + warp * 4 * (DH * 4) + lane * 16);
        const uint32_t vs_off = (uint32_t)(OFF_K + KV_TILE_BYTES + (warp * 4 + g) * 2);
        const uint32_t vz_off = (uint32_t)(OFF_K + KV_TILE_BYTES + SC_BYTES + warp * 8);
        while (true) {
            mbar_wait(bar_fk + sk * 8, phk);
            const int desc = tile_ids[sk];
            const uint32_t stk = sb + sk * KSLOT_BYTES;
            const bool active = (desc >= 0) && ((NHALF == 0) || !(desc & 1) || (warp < NCW / 2));
            int4 kq[4];
            float vs = 0.f;
            uint2 vzp = make_uint2(0u, 0u);
            if (active) {
#pragma unroll
                for (int j = 0; j < 4; j++) kq[j] = lds128(stk + k_off + j * 128);
                vs = lds_bf16(stk + vs_off);
                vzp = lds64(stk + vz_off);
            }
            __syncwarp();
            if (lane == 0) mbar_arrive(bar_ek + sk * 8);
            if (++sk == NK) { sk = 0; phk ^= 1; }

            const int seg = desc < 0 ? NGK * HKV : desc / (2 * UNITS_PER_SEG);
            if (seg != cur_seg) {
                const int head = seg / NGK;
                if (cur_seg < 0 || head != cur_head) {
                    flush(cur_seg >= 0, head);
                    if (desc < 0) break;
                    m = NEG_BIG;
                    l = 0.f;
#pragma unroll
                    for (int i = 0; i < 4; i++) acc0[i] = acc1[i] = 0.f;
                }
                cur_seg = seg;
                const float4* tp = reinterpret_cast<const float4*>(smem + OFF_TAB) + seg * (2 * DH / 4) + c;
#pragma unroll
                for (int j = 0; j < 4; j++) {
                    const float4 x0 = tp[8 * j], x1 = tp[DH / 4 + 8 * j];
                    a0[4 * j] = x0.x; a0[4 * j + 1] = x0.y; a0[4 * j + 2] = x0.z; a0[4 * j + 3] = x0.w;
                    a1[4 * j] = x1.x; a1[4 * j + 1] = x1.y; a1[4 * j + 2] = x1.z; a1[4 * j + 3] = x1.w;
                }
                bias = reinterpret_cast<const float*>(smem + OFF_BIAS)[seg * 2 + par];
            }

            if (active) {
                float s0a = 0.f, s0b = 0.f, s1a = 0.f, s1b = 0.f;
#pragma unroll
                for (int j = 0; j < 4; j++) {
                    const float k0 = (float)kq[j].x, k1 = (float)kq[j].y, k2 = (float)kq[j].z, k3 = (float)kq[j].w;
                    s0a = fmaf(a0[4 * j + 0], k0, s0a);
                    s1a = fmaf(a1[4 * j + 0], k0, s1a);
                    s0b = fmaf(a0[4 * j + 1], k1, s0b);
                    s1b = fmaf(a1[4 * j + 1], k1, s1b);
                    s0a = fmaf(a0[4 * j + 2], k2, s0a);
                    s1a = fmaf(a1[4 * j + 2], k2, s1a);
                    s0b = fmaf(a0[4 * j + 3], k3, s0b);
                    s1b = fmaf(a1[4 * j + 3], k3, s1b);
                }
                const float s0 = s0a + s0b, s1 = s1a + s1b;
                float y = (par ? s1 : s0) + __shfl_xor_sync(0xffffffffu, par ? s0 : s1, 1);
                y += __shfl_xor_sync(0xffffffffu, y, 2);
                y += __shfl_xor_sync(0xffffffffu, y, 4);
                const float sl = y - bias;

                float mt = fmaxf(sl, __shfl_xor_sync(0xffffffffu, sl, 8));
                mt = fmaxf(mt, __shfl_xor_sync(0xffffffffu, mt, 16));
                const float mn = fmaxf(m, mt);
                const float p = ex2(sl - mn);
                const float al = ex2(m - mn);
                m = mn;
                l = fmaf(l, al, p);
                const float w = p * vs;
                const float al0 = __shfl_sync(0xffffffffu, al, 0), al1 = __shfl_sync(0xffffffffu, al, 1);
                float w0[4], w1[4];
#pragma unroll
                for (int j = 0; j < 4; j++) {
                    w0[j] = __shfl_sync(0xffffffffu, w, 8 * j);
                    w1[j] = __shfl_sync(0xffffffffu, w, 8 * j + 1);
                }
#pragma unroll
                for (int i = 0; i < 4; i++) { acc0[i] *= al0; acc1[i] *= al1; }
                float vz[4];
                vz[0] = bf_lo(vzp.x);
                vz[1] = bf_hi(vzp.x);
                vz[2] = bf_lo(vzp.y);
                vz[3] = bf_hi(vzp.y);

                mbar_wait(bar_fv + sv * 8, phv);
                int4 vq[4];
#pragma unroll
                for (int j = 0; j < 4; j++) vq[j] = lds128(sb + sv * KV_TILE_BYTES + v_off + j * (DH * 4));
                __syncwarp();
                if (lane == 0) mbar_arrive(bar_ev + sv * 8);
#pragma unroll
                for (int j = 0; j < 4; j++) {
                    const float v0 = (float)vq[j].x - vz[j], v1 = (float)vq[j].y - vz[j], v2 = (float)vq[j].z - vz[j],
                                v3 = (float)vq[j].w - vz[j];
                    acc0[0] = fmaf(w0[j], v0, acc0[0]);
                    acc1[0] = fmaf(w1[j], v0, acc1[0]);
                    acc0[1] = fmaf(w0[j], v1, acc0[1]);
                    acc1[1] = fmaf(w1[j], v1, acc1[1]);
                    acc0[2] = fmaf(w0[j], v2, acc0[2]);
                    acc1[2] = fmaf(w1[j], v2, acc1[2]);
                    acc0[3] = fmaf(w0[j], v3, acc0[3]);
                    acc1[3] = fmaf(w1[j], v3, acc1[3]);
                }
            } else {
                mbar_wait(bar_fv + sv * 8, phv);
                if (lane == 0) mbar_arrive(bar_ev + sv * 8);
            }
            if (++sv == NV) { sv = 0; phv ^= 1; }
        }
    }
}

}

extern "C" void kernel_launch(void* const* d_in, const int* in_sizes, int n_in, void* d_out, int out_size) {
    (void)in_sizes; (void)n_in; (void)out_size;
    static int grid = 0;
    if (grid == 0) {
        int dev = 0, sms = 0;
        cudaGetDevice(&dev);
        cudaDeviceGetAttribute(&sms, cudaDevAttrMultiProcessorCount, dev);
        cudaFuncSetAttribute(kvq::kvq_decode_kernel, cudaFuncAttributeMaxDynamicSharedMemorySize, kvq::SMEM_BYTES);
        grid = sms < kvq::MAXG ? sms : kvq::MAXG;
    }
    kvq::kvq_decode_kernel<<<grid, kvq::NTHREADS, kvq::SMEM_BYTES>>>(
        (const __nv_bfloat16*)d_in[0], (const int*)d_in[1], (const int*)d_in[2], (const __nv_bfloat16*)d_in[3],
        (const __nv_bfloat16*)d_in[4], (const __nv_bfloat16*)d_in[5], (const __nv_bfloat16*)d_in[6],
        (__nv_bfloat16*)d_out);
}
```

```cpp
#include <cuda_runtime.h>
#include <cuda_bf16.h>
#include <stdint.h>

namespace kvq {

constexpr int HKV = 16;
constexpr int SKV = 65536;
constexpr int DH = 128;
constexpr int NGK = 2;
constexpr int NSEG = HKV * NGK;
constexpr int TILE = 32;
constexpr int UNIT = 16;
constexpr int UNITS_PER_SEG = SKV / NGK / UNIT;
constexpr int NUNITS = HKV * SKV / UNIT;
constexpr int RING = 2;
constexpr int NHALF = 528;
constexpr int NFULL = (NUNITS - NHALF) / 2;
constexpr int NTICKETS = NFULL + NHALF;
constexpr int NSLOT = 2;
constexpr int KV_TILE_BYTES = TILE * DH * 4;
constexpr int SC_BYTES = TILE * 2;
constexpr int KSLOT_BYTES = KV_TILE_BYTES + 2 * SC_BYTES;
constexpr int NCW = 8;
constexpr int NTHREADS = (NCW + 2) * 32;
constexpr int MAXG = 160;
constexpr int NSLICE = 128;

constexpr int OFF_K = 0;
constexpr int OFF_V = OFF_K + RING * KSLOT_BYTES;
constexpr int PARAM_BYTES = NSEG * DH * 2;
constexpr int OFF_Q = OFF_V + RING * KV_TILE_BYTES;
constexpr int OFF_KS = OFF_Q + PARAM_BYTES;
constexpr int OFF_KZ = OFF_KS + PARAM_BYTES;
constexpr int OFF_RED = OFF_KZ + PARAM_BYTES;
constexpr int OFF_ML = OFF_RED + NCW * 2 * DH * 4;
constexpr int OFF_BAR = OFF_ML + NCW * 2 * 8;
constexpr int OFF_TID = OFF_BAR + (4 * RING + 1) * 8;
constexpr int OFF_FLAG = OFF_TID + RING * 4;
constexpr int SMEM_BYTES = OFF_FLAG + 8;

constexpr float NEG_BIG = -3.0e38f;

__device__ uint4 g_part[NSLOT * MAXG * NSLICE];
__device__ unsigned int g_sync[2];

__device__ __forceinline__ uint32_t smem_u32(const void* p) { return (uint32_t)__cvta_generic_to_shared(p); }
__device__ __forceinline__ void mbar_init(uint32_t bar, uint32_t cnt) {
    asm volatile("mbarrier.init.shared::cta.b64 [%0], %1;" ::"r"(bar), "r"(cnt) : "memory");
}
__device__ __forceinline__ void mbar_expect_tx(uint32_t bar, uint32_t bytes) {
    asm volatile("mbarrier.arrive.expect_tx.shared::cta.b64 _, [%0], %1;" ::"r"(bar), "r"(bytes) : "memory");
}
__device__ __forceinline__ void mbar_arrive(uint32_t bar) {
    asm volatile("mbarrier.arrive.shared::cta.b64 _, [%0];" ::"r"(bar) : "memory");
}
__device__ __forceinline__ void mbar_wait(uint32_t bar, uint32_t parity) {
    uint32_t done;
    uint32_t it = 0;
    do {
        asm volatile(
            "{\n.reg .pred p;\n"
            "mbarrier.try_wait.parity.shared::cta.b64 p, [%1], %2;\n"
            "selp.u32 %0, 1, 0, p;\n}"
            : "=r"(done)
            : "r"(bar), "r"(parity)
            : "memory");
        if (++it > (1u << 26)) __trap();
    } while (!done);
}
__device__ __forceinline__ uint4 ldg128(const void* p) {
    uint4 v;
    asm volatile("ld.global.nc.v4.u32 {%0,%1,%2,%3}, [%4];" : "=r"(v.x), "=r"(v.y), "=r"(v.z), "=r"(v.w) : "l"(p));
    return v;
}
__device__ __forceinline__ float bf_lo(uint32_t x) { return __uint_as_float(x << 16); }
__device__ __forceinline__ float bf_hi(uint32_t x) { return __uint_as_float(x & 0xffff0000u); }
__device__ __forceinline__ uint32_t dequant2(int x0, int x1, uint32_t z2, uint32_t s2) {
    uint32_t r;
    asm("{\n.reg .b32 t;\n"
        "cvt.rn.bf16x2.f32 t, %2, %1;\n"
        "sub.rn.bf16x2 t, t, %3;\n"
        "mul.rn.bf16x2 %0, t, %4;\n}"
        : "=r"(r)
        : "f"((float)x0), "f"((float)x1), "r"(z2), "r"(s2));
    return r;
}
__device__ __forceinline__ float round_bf16(float x) { return __bfloat162float(__float2bfloat16_rn(x)); }
__device__ __forceinline__ void bulk_g2s(uint32_t dst, const void* src, uint32_t bytes, uint32_t bar, uint64_t pol) {
    asm volatile(
        "cp.async.bulk.shared::cluster.global.mbarrier::complete_tx::bytes.L2::cache_hint [%0], [%1], %2, [%3], %4;" ::"r"(dst),
        "l"(src), "r"(bytes), "r"(bar), "l"(pol)
        : "memory");
}
__device__ __forceinline__ unsigned int draw_ticket(unsigned int* p, unsigned int last) {
    unsigned int v;
    asm volatile("atom.relaxed.gpu.global.inc.u32 %0, [%1], %2;" : "=r"(v) : "l"(p), "r"(last) : "memory");
    return v;
}
__device__ __forceinline__ float ex2(float x) {
    float y;
    asm("ex2.approx.ftz.f32 %0, %1;" : "=f"(y) : "f"(x));
    return y;
}
__device__ __forceinline__ int4 lds128(uint32_t addr) {
    int4 v;
    asm volatile("ld.shared.v4.s32 {%0,%1,%2,%3}, [%4];" : "=r"(v.x), "=r"(v.y), "=r"(v.z), "=r"(v.w) : "r"(addr));
    return v;
}
__device__ __forceinline__ uint2 lds64(uint32_t addr) {
    uint2 v;
    asm volatile("ld.shared.v2.u32 {%0,%1}, [%2];" : "=r"(v.x), "=r"(v.y) : "r"(addr));
    return v;
}
__device__ __forceinline__ float lds_bf16(uint32_t addr) {
    unsigned short v;
    asm volatile("ld.shared.u16 %0, [%1];" : "=h"(v) : "r"(addr));
    return __uint_as_float(((uint32_t)v) << 16);
}
__device__ __forceinline__ void st_chunk(uint4* p, uint32_t a, uint32_t b, uint32_t c, uint32_t d) {
    asm volatile(
        "{\n.reg .b64 lo, hi;\n.reg .b128 t;\n"
        "mov.b64 lo, {%1,%2};\nmov.b64 hi, {%3,%4};\nmov.b128 t, {lo,hi};\n"
        "st.relaxed.gpu.global.b128 [%0], t;\n}" ::"l"(p),
        "r"(a), "r"(b), "r"(c), "r"(d)
        : "memory");
}
__device__ __forceinline__ void ld_chunks5(ulonglong2 (&v)[5], const uint4* p, uint32_t pend) {
    asm volatile(
        "{\n.reg .pred p0, p1, p2, p3, p4;\n.reg .b32 t;\n.reg .b128 c0, c1, c2, c3, c4;\n"
        "and.b32 t, %11, 1;  setp.ne.u32 p0, t, 0;\n"
        "and.b32 t, %11, 2;  setp.ne.u32 p1, t, 0;\n"
        "and.b32 t, %11, 4;  setp.ne.u32 p2, t, 0;\n"
        "and.b32 t, %11, 8;  setp.ne.u32 p3, t, 0;\n"
        "and.b32 t, %11, 16; setp.ne.u32 p4, t, 0;\n"
        "mov.b128 c0, {%0,%1};\nmov.b128 c1, {%2,%3};\nmov.b128 c2, {%4,%5};\nmov.b128 c3, {%6,%7};\nmov.b128 c4, {%8,%9};\n"
        "@p0 ld.relaxed.gpu.global.b128 c0, [%10];\n"
        "@p1 ld.relaxed.gpu.global.b128 c1, [%10+65536];\n"
        "@p2 ld.relaxed.gpu.global.b128 c2, [%10+131072];\n"
        "@p3 ld.relaxed.gpu.global.b128 c3, [%10+196608];\n"
        "@p4 ld.relaxed.gpu.global.b128 c4, [%10+262144];\n"
        "mov.b128 {%0,%1}, c0;\nmov.b128 {%2,%3}, c1;\nmov.b128 {%4,%5}, c2;\nmov.b128 {%6,%7}, c3;\nmov.b128 {%8,%9}, c4;\n"
        "}"
        : "+l"(v[0].x), "+l"(v[0].y), "+l"(v[1].x), "+l"(v[1].y), "+l"(v[2].x), "+l"(v[2].y), "+l"(v[3].x),
          "+l"(v[3].y), "+l"(v[4].x), "+l"(v[4].y)
        : "l"(p), "r"(pend)
        : "memory");
}
static_assert(MAXG == 160 && NSLICE * 32 * 16 == 65536, "ld_chunks5 layout");
__device__ __forceinline__ float lo_f(unsigned long long x) { return __uint_as_float((uint32_t)x); }
__device__ __forceinline__ float hi_f(unsigned long long x) { return __uint_as_float((uint32_t)(x >> 32)); }
__device__ __forceinline__ void consumer_bar() { asm volatile("bar.sync 1, %0;" ::"n"(NCW * 32) : "memory"); }
__device__ __forceinline__ float warp_max(float x) {
    int i = __float_as_int(x);
    i ^= (i >> 31) & 0x7fffffff;
    i = __reduce_max_sync(0xffffffffu, i);
    i ^= (i >> 31) & 0x7fffffff;
    return __int_as_float(i);
}

__global__ void __launch_bounds__(NTHREADS, 1)
kvq_decode_kernel(const __nv_bfloat16* __restrict__ q, const int* __restrict__ qk, const int* __restrict__ qv,
                  const __nv_bfloat16* __restrict__ k_scales, const __nv_bfloat16* __restrict__ k_zeros,
                  const __nv_bfloat16* __restrict__ v_scales, const __nv_bfloat16* __restrict__ v_zeros,
                  __nv_bfloat16* __restrict__ out, unsigned int* __restrict__ sync, uint4* __restrict__ part)
{
    extern __shared__ __align__(128) unsigned char smem[];
    const uint32_t sb = smem_u32(smem);
    const int tid = threadIdx.x, warp = tid >> 5, lane = tid & 31;
    const int G = gridDim.x, cta = blockIdx.x;
    const uint32_t bar_fk = sb + OFF_BAR, bar_ek = bar_fk + RING * 8, bar_fv = bar_ek + RING * 8,
                   bar_ev = bar_fv + RING * 8, bar_post = bar_ev + RING * 8;
    volatile int* tile_ids = reinterpret_cast<volatile int*>(smem + OFF_TID);
    volatile int* combined = reinterpret_cast<volatile int*>(smem + OFF_FLAG);
    volatile uint32_t* tagbase = reinterpret_cast<volatile uint32_t*>(combined + 1);
    const unsigned int last_draw = (unsigned int)(NTICKETS - RING * G + G - 1);
    unsigned int draw = 0, epoch = 0;

    uint64_t pol;
    asm volatile("createpolicy.fractional.L2::evict_first.b64 %0, 1.0;" : "=l"(pol));
    auto issue_k = [&](int s, int u, bool half) {
        const uint32_t kvb = half ? KV_TILE_BYTES / 2 : KV_TILE_BYTES;
        const uint32_t scb = half ? SC_BYTES / 2 : SC_BYTES;
        const uint32_t fk = bar_fk + s * 8;
        const uint32_t dst = sb + OFF_K + s * KSLOT_BYTES;
        tile_ids[s] = u * 2 + (half ? 1 : 0);
        mbar_expect_tx(fk, kvb + 2 * scb);
        bulk_g2s(dst, qk + (size_t)u * (UNIT * DH), kvb, fk, pol);
        bulk_g2s(dst + KV_TILE_BYTES, v_scales + (size_t)u * UNIT, scb, fk, pol);
        bulk_g2s(dst + KV_TILE_BYTES + SC_BYTES, v_zeros + (size_t)u * UNIT, scb, fk, pol);
    };
    auto issue_v = [&](int s, int u, bool half) {
        const uint32_t kvb = half ? KV_TILE_BYTES / 2 : KV_TILE_BYTES;
        const uint32_t fv = bar_fv + s * 8;
        mbar_expect_tx(fv, kvb);
        bulk_g2s(sb + OFF_V + s * KV_TILE_BYTES, qv + (size_t)u * (UNIT * DH), kvb, fv, pol);
    };

    uint4 pq0, pq1, pks0, pks1, pkz0, pkz1;
    if (warp < NCW) {
        const int off = (tid >> 4) * (2 * DH) + (tid & 15) * 8;
        pq0 = ldg128(q + off);
        pq1 = ldg128(q + off + DH);
        pks0 = ldg128(k_scales + off);
        pks1 = ldg128(k_scales + off + DH);
        pkz0 = ldg128(k_zeros + off);
        pkz1 = ldg128(k_zeros + off + DH);
    } else if (lane == 0) {
        if (warp == NCW) {
            asm volatile("ld.relaxed.gpu.global.u32 %0, [%1];" : "=r"(epoch) : "l"(sync + 1) : "memory");
            draw = draw_ticket(sync, last_draw);
            *combined = 0;
            mbar_init(bar_post, 1);
#pragma unroll
            for (int s = 0; s < RING; s++) {
                mbar_init(bar_ek + s * 8, NCW);
                mbar_init(bar_ev + s * 8, NCW);
            }
        } else {
#pragma unroll
            for (int s = 0; s < RING; s++) {
                mbar_init(bar_fk + s * 8, 1);
                mbar_init(bar_fv + s * 8, 1);
            }
            asm volatile("fence.proxy.async.shared::cta;" ::: "memory");
#pragma unroll
            for (int s = 0; s < RING; s++) {
                const int u = 2 * (cta + s * G);
                issue_k(s, u, false);
                issue_v(s, u, false);
            }
        }
    }
    __syncthreads();

    if (warp == NCW) {
        if (lane == 0) {
            *tagbase = epoch * 16u + 1u;
            int s = 0;
            uint32_t ph = 0;
            while (true) {
                mbar_wait(bar_ek + s * 8, ph);
                if (draw == ~0u) draw = draw_ticket(sync, last_draw);
                const int t = (int)draw + RING * G;
                if (t >= NTICKETS) {
                    tile_ids[s] = -1;
                    mbar_arrive(bar_fk + s * 8);
                    if (draw == last_draw)
                        asm volatile("st.relaxed.gpu.global.u32 [%0], %1;" ::"l"(sync + 1), "r"(epoch + 1u) : "memory");
                    break;
                }
                draw = ~0u;
                const bool half = t >= NFULL;
                const int u = half ? (t + NFULL) : (2 * t);
                issue_k(s, u, half);
                mbar_wait(bar_ev + s * 8, ph);
                issue_v(s, u, half);
                if (++s == RING) { s = 0; ph ^= 1; }
            }
        }
    } else if (warp == NCW + 1) {
        constexpr int KMAX = MAXG / 32;
        uint32_t valid = 0;
#pragma unroll
        for (int k = 0; k < KMAX; k++) valid |= (lane + 32 * k < G) ? (1u << k) : 0u;
        for (int h = 0; h < HKV; h++) {
            __syncwarp();
            mbar_wait(bar_post, (uint32_t)(h & 1));
            __syncwarp();
            if (h != HKV - 1) {
#pragma unroll 1
                for (int i = 0; i < 4; i++) __nanosleep(1000);
            }
            const uint32_t tag = *tagbase + (uint32_t)h;
            for (int jj = cta; jj < NSLICE || jj == cta; jj += G) {
                const int j = jj % NSLICE;
                const uint4* base = part + ((size_t)(h % NSLOT) * MAXG + lane) * NSLICE + j;
                ulonglong2 v[KMAX];
#pragma unroll
                for (int k = 0; k < KMAX; k++)
                    v[k] = make_ulonglong2(0ull, ((unsigned long long)tag << 32) | __float_as_uint(NEG_BIG));
                uint32_t pend = valid;
                uint32_t it = 0;
                while (true) {
                    ld_chunks5(v, base, pend);
#pragma unroll
                    for (int k = 0; k < KMAX; k++)
                        if ((uint32_t)(v[k].y >> 32) == tag) pend &= ~(1u << k);
                    if (__all_sync(0xffffffffu, pend == 0u)) break;
                    if (h != HKV - 1) __nanosleep(500);
                    if (++it > (1u << 24)) __trap();
                }
                float M = NEG_BIG;
#pragma unroll
                for (int k = 0; k < KMAX; k++) M = fmaxf(M, lo_f(v[k].y));
                M = warp_max(M);
                float a0 = 0.f, a1 = 0.f, L = 0.f;
#pragma unroll
                for (int k = 0; k < KMAX; k++) {
                    const float f = ex2(lo_f(v[k].y) - M);
                    a0 = fmaf(f, lo_f(v[k].x), a0);
                    a1 = fmaf(f, hi_f(v[k].x), a1);
                    L += f;
                }
#pragma unroll
                for (int o = 16; o > 0; o >>= 1) {
                    a0 += __shfl_xor_sync(0xffffffffu, a0, o);
                    a1 += __shfl_xor_sync(0xffffffffu, a1, o);
                    L += __shfl_xor_sync(0xffffffffu, L, o);
                }
                if (lane == 0 && jj < NSLICE) {
                    __nv_bfloat162 o2 = __floats2bfloat162_rn(__fdividef(a0, L), __fdividef(a1, L));
                    *reinterpret_cast<__nv_bfloat162*>(out + (2 * h + (j >> 6)) * DH + 2 * (j & 63)) = o2;
                }
                __syncwarp();
            }
            if (lane == 0) *combined = h + 1;
        }
    } else {
        const int g = lane >> 3, c = lane & 7, par = lane & 1;
        float a0[16], a1[16], acc0[4], acc1[4];
        uint32_t ks2[8], kz2[8];
        float m = NEG_BIG, l = 0.f;
#pragma unroll
        for (int i = 0; i < 16; i++) a0[i] = a1[i] = 0.f;
#pragma unroll
        for (int i = 0; i < 8; i++) ks2[i] = kz2[i] = 0u;
#pragma unroll
        for (int i = 0; i < 4; i++) acc0[i] = acc1[i] = 0.f;
        int cur_seg = -1, cur_head = 0;
        float* red = reinterpret_cast<float*>(smem + OFF_RED);
        float2* ml = reinterpret_cast<float2*>(smem + OFF_ML);
        uint4* mybox = part + (size_t)cta * NSLICE + tid;

        auto wait_combined = [&](int h) {
            uint32_t it = 0;
            while (*combined < h) {
                __nanosleep(100);
                if (++it > (1u << 26)) __trap();
            }
        };
        auto flush = [&](bool have, int upto) {
            if (have) {
                float ls = l + __shfl_xor_sync(0xffffffffu, l, 8);
                ls += __shfl_xor_sync(0xffffffffu, ls, 16);
                float* dst = red + warp * 2 * DH + 4 * lane;
                *reinterpret_cast<float4*>(dst) = make_float4(acc0[0], acc0[1], acc0[2], acc0[3]);
                *reinterpret_cast<float4*>(dst + DH) = make_float4(acc1[0], acc1[1], acc1[2], acc1[3]);
                if (lane < 2) ml[warp * 2 + lane] = make_float2(m, ls);
                const uint32_t tag = *tagbase + (uint32_t)cur_head;
                wait_combined(cur_head);
                consumer_bar();
                if (tid < NSLICE) {
                    const int hh = tid >> 6, d = 2 * (tid & 63);
                    float2 w[NCW], xv[NCW];
#pragma unroll
                    for (int i = 0; i < NCW; i++) w[i] = ml[i * 2 + hh];
#pragma unroll
                    for (int i = 0; i < NCW; i++) xv[i] = *reinterpret_cast<const float2*>(red + (i * 2 + hh) * DH + d);
                    const float M = fmaxf(fmaxf(fmaxf(w[0].x, w[1].x), fmaxf(w[2].x, w[3].x)),
                                          fmaxf(fmaxf(w[4].x, w[5].x), fmaxf(w[6].x, w[7].x)));
                    float x0 = 0.f, x1 = 0.f, L = 0.f;
#pragma unroll
                    for (int i = 0; i < NCW; i++) {
                        const float f = ex2(w[i].x - M);
                        x0 = fmaf(f, xv[i].x, x0);
                        x1 = fmaf(f, xv[i].y, x1);
                        L = fmaf(f, w[i].y, L);
                    }
                    st_chunk(mybox + (size_t)(cur_head % NSLOT) * MAXG * NSLICE, __float_as_uint(__fdividef(x0, L)),
                             __float_as_uint(__fdividef(x1, L)), __float_as_uint(M + __log2f(L)), tag);
                    if (tid == 0) mbar_arrive(bar_post);
                }
                cur_head++;
            }
            for (; cur_head < upto; cur_head++) {
                if (tid < NSLICE) {
                    wait_combined(cur_head);
                    st_chunk(mybox + (size_t)(cur_head % NSLOT) * MAXG * NSLICE, 0u, 0u, __float_as_uint(NEG_BIG),
                             *tagbase + (uint32_t)cur_head);
                    if (tid == 0) mbar_arrive(bar_post);
                }
            }
            if (have) consumer_bar();
            __syncwarp();
        };

        {
            const int off = ((tid >> 4) * (2 * DH) + (tid & 15) * 8) * 2;
            *reinterpret_cast<uint4*>(smem + OFF_Q + off) = pq0;
            *reinterpret_cast<uint4*>(smem + OFF_Q + off + 2 * DH) = pq1;
            *reinterpret_cast<uint4*>(smem + OFF_KS + off) = pks0;
            *reinterpret_cast<uint4*>(smem + OFF_KS + off + 2 * DH) = pks1;
            *reinterpret_cast<uint4*>(smem + OFF_KZ + off) = pkz0;
            *reinterpret_cast<uint4*>(smem + OFF_KZ + off + 2 * DH) = pkz1;
            consumer_bar();
        }

        int s = 0;
        uint32_t ph = 0;
        const uint32_t k_off = (uint32_t)(OFF_K + (warp * 4 + g) * (DH * 4) + c * 16);
        const uint32_t v_off = (uint32_t)(OFF_V + warp * 4 * (DH * 4) + lane * 16);
        const uint32_t vs_off = (uint32_t)(OFF_K + KV_TILE_BYTES + (warp * 4 + g) * 2);
        const uint32_t vz_off = (uint32_t)(OFF_K + KV_TILE_BYTES + SC_BYTES + warp * 8);
        while (true) {
            mbar_wait(bar_fk + s * 8, ph);
            const int desc = tile_ids[s];
            const uint32_t stk = sb + s * KSLOT_BYTES;
            const bool active = (desc >= 0) && (!(desc & 1) || (warp < NCW / 2));
            int4 kq[4];
            float vs = 0.f;
            uint2 vzp = make_uint2(0u, 0u);
            if (active) {
#pragma unroll
                for (int j = 0; j < 4; j++) kq[j] = lds128(stk + k_off + j * 128);
                vs = lds_bf16(stk + vs_off);
                vzp = lds64(stk + vz_off);
            }
            __syncwarp();
            if (lane == 0) mbar_arrive(bar_ek + s * 8);

            const int seg = desc < 0 ? NSEG : desc / (2 * UNITS_PER_SEG);
            if (seg != cur_seg) {
                const int head = seg / NGK;
                if (cur_seg < 0 || head != cur_head) {
                    flush(cur_seg >= 0, head);
                    if (desc < 0) break;
                    m = NEG_BIG;
                    l = 0.f;
#pragma unroll
                    for (int i = 0; i < 4; i++) acc0[i] = acc1[i] = 0.f;
                }
                cur_seg = seg;
#pragma unroll
                for (int j = 0; j < 4; j++) {
                    const uint32_t o = (uint32_t)(j * 64 + c * 8);
                    const uint2 x0 = lds64(sb + OFF_Q + head * (4 * DH) + o);
                    const uint2 x1 = lds64(sb + OFF_Q + head * (4 * DH) + 2 * DH + o);
                    const uint2 xs = lds64(sb + OFF_KS + seg * (2 * DH) + o);
                    const uint2 xz = lds64(sb + OFF_KZ + seg * (2 * DH) + o);
                    a0[4 * j] = bf_lo(x0.x); a0[4 * j + 1] = bf_hi(x0.x); a0[4 * j + 2] = bf_lo(x0.y); a0[4 * j + 3] = bf_hi(x0.y);
                    a1[4 * j] = bf_lo(x1.x); a1[4 * j + 1] = bf_hi(x1.x); a1[4 * j + 2] = bf_lo(x1.y); a1[4 * j + 3] = bf_hi(x1.y);
                    ks2[2 * j] = xs.x; ks2[2 * j + 1] = xs.y;
                    kz2[2 * j] = xz.x; kz2[2 * j + 1] = xz.y;
                }
            }

            if (active) {
                float s0a = 0.f, s0b = 0.f, s1a = 0.f, s1b = 0.f;
#pragma unroll
                for (int j = 0; j < 4; j++) {
                    const uint32_t k01 = dequant2(kq[j].x, kq[j].y, kz2[2 * j], ks2[2 * j]);
                    const uint32_t k23 = dequant2(kq[j].z, kq[j].w, kz2[2 * j + 1], ks2[2 * j + 1]);
                    const float k0 = bf_lo(k01), k1 = bf_hi(k01), k2 = bf_lo(k23), k3 = bf_hi(k23);
                    s0a = fmaf(a0[4 * j + 0], k0, s0a);
                    s1a = fmaf(a1[4 * j + 0], k0, s1a);
                    s0b = fmaf(a0[4 * j + 1], k1, s0b);
                    s1b = fmaf(a1[4 * j + 1], k1, s1b);
                    s0a = fmaf(a0[4 * j + 2], k2, s0a);
                    s1a = fmaf(a1[4 * j + 2], k2, s1a);
                    s0b = fmaf(a0[4 * j + 3], k3, s0b);
                    s1b = fmaf(a1[4 * j + 3], k3, s1b);
                }
                const float s0 = s0a + s0b, s1 = s1a + s1b;
                float y = (par ? s1 : s0) + __shfl_xor_sync(0xffffffffu, par ? s0 : s1, 1);
                y += __shfl_xor_sync(0xffffffffu, y, 2);
                y += __shfl_xor_sync(0xffffffffu, y, 4);
                const float sl = round_bf16(round_bf16(y) * 0.08838834764831845f) * 1.4426950408889634f;

                float mt = fmaxf(sl, __shfl_xor_sync(0xffffffffu, sl, 8));
                mt = fmaxf(mt, __shfl_xor_sync(0xffffffffu, mt, 16));
                const float mn = fmaxf(m, mt);
                const float p = ex2(sl - mn);
                const float al = ex2(m - mn);
                m = mn;
                l = fmaf(l, al, p);
                const float w = p * vs;
                const float al0 = __shfl_sync(0xffffffffu, al, 0), al1 = __shfl_sync(0xffffffffu, al, 1);
                float w0[4], w1[4];
#pragma unroll
                for (int j = 0; j < 4; j++) {
                    w0[j] = __shfl_sync(0xffffffffu, w, 8 * j);
                    w1[j] = __shfl_sync(0xffffffffu, w, 8 * j + 1);
                }
#pragma unroll
                for (int i = 0; i < 4; i++) { acc0[i] *= al0; acc1[i] *= al1; }
                const float vz[4] = {bf_lo(vzp.x), bf_hi(vzp.x), bf_lo(vzp.y), bf_hi(vzp.y)};

                mbar_wait(bar_fv + s * 8, ph);
                int4 vq[4];
#pragma unroll
                for (int j = 0; j < 4; j++) vq[j] = lds128(sb + s * KV_TILE_BYTES + v_off + j * (DH * 4));
                __syncwarp();
                if (lane == 0) mbar_arrive(bar_ev + s * 8);
#pragma unroll
                for (int j = 0; j < 4; j++) {
                    const float v0 = (float)vq[j].x - vz[j], v1 = (float)vq[j].y - vz[j], v2 = (float)vq[j].z - vz[j],
                                v3 = (float)vq[j].w - vz[j];
                    acc0[0] = fmaf(w0[j], v0, acc0[0]);
                    acc1[0] = fmaf(w1[j], v0, acc1[0]);
                    acc0[1] = fmaf(w0[j], v1, acc0[1]);
                    acc1[1] = fmaf(w1[j], v1, acc1[1]);
                    acc0[2] = fmaf(w0[j], v2, acc0[2]);
                    acc1[2] = fmaf(w1[j], v2, acc1[2]);
                    acc0[3] = fmaf(w0[j], v3, acc0[3]);
                    acc1[3] = fmaf(w1[j], v3, acc1[3]);
                }
            } else {
                mbar_wait(bar_fv + s * 8, ph);
                __syncwarp();
                if (lane == 0) mbar_arrive(bar_ev + s * 8);
            }
            if (++s == RING) { s = 0; ph ^= 1; }
        }
    }
}

}

extern "C" void kernel_launch(void* const* d_in, const int* in_sizes, int n_in, void* d_out, int out_size) {
    (void)in_sizes; (void)n_in; (void)out_size;
    static int grid = 0;
    static void* sync = nullptr;
    static void* part = nullptr;
    if (grid == 0) {
        cudaGetSymbolAddress(&sync, kvq::g_sync);
        cudaGetSymbolAddress(&part, kvq::g_part);
        int dev = 0, sms = 0;
        cudaGetDevice(&dev);
        cudaDeviceGetAttribute(&sms, cudaDevAttrMultiProcessorCount, dev);
        cudaFuncSetAttribute(kvq::kvq_decode_kernel, cudaFuncAttributeMaxDynamicSharedMemorySize, kvq::SMEM_BYTES);
        grid = sms < kvq::MAXG ? sms : kvq::MAXG;
    }
    kvq::kvq_decode_kernel<<<grid, kvq::NTHREADS, kvq::SMEM_BYTES>>>(
        (const __nv_bfloat16*)d_in[0], (const int*)d_in[1], (const int*)d_in[2], (const __nv_bfloat16*)d_in[3],
        (const __nv_bfloat16*)d_in[4], (const __nv_bfloat16*)d_in[5], (const __nv_bfloat16*)d_in[6],
        (__nv_bfloat16*)d_out, (unsigned int*)sync, (uint4*)part);
}
```
